```python
import torch

def _softmax(x, axis=-1):
    return torch.softmax(x, dim=axis)
def _gelu(x):
    return torch.nn.functional.gelu(x, approximate="tanh")
def _silu(x):
    return torch.nn.functional.silu(x)
def _sigmoid(x):
    return torch.sigmoid(x)
def _layernorm(x, axis=-1, eps=1e-5):
    m = x.mean(dim=axis, keepdim=True)
    v = x.var(dim=axis, keepdim=True, unbiased=False)
    return (x - m) / torch.sqrt(v + eps)
def _scatter_add(tgt, idx, src, axis=0):
    return tgt.clone().index_add_(axis, idx, src)
def _segment_sum(src, seg, n):
    out = torch.zeros((n,) + src.shape[1:], dtype=src.dtype)
    return out.index_add_(0, seg, src)
def _pad(x, pw):
    flat = tuple(v for pair in reversed(pw) for v in pair)
    return torch.nn.functional.pad(x, flat)

kernel_name = 'standalone__gqa_softmax__near_ridge'

def setup_inputs():

    _w = (lambda a: (lambda t: t.to(torch.bfloat16) if t.is_floating_point() else t)(torch.as_tensor(a)))
    B, Hq, Hkv, Sq, Sk, D = 8, 32, 32, 608, 1024, 128
    return {
        "q": _w((lambda *s: torch.randn(*s, dtype=torch.bfloat16) * 0.8)(B, Hq, Sq, D)),
        "k": _w((lambda *s: torch.randn(*s, dtype=torch.bfloat16) * 0.8)(B, Hkv, Sk, D)),
        "v": _w((lambda *s: torch.randn(*s, dtype=torch.bfloat16) * 0.05)(B, Hkv, Sk, D)),
    }

def reference(q, k, v):
    B, Hq, Sq, D = q.shape
    Hkv = k.shape[1]
    rep = Hq // Hkv
    k = (lambda x, n, axis: torch.repeat_interleave(x, n, dim=axis))(k, rep, axis=1)
    v = (lambda x, n, axis: torch.repeat_interleave(x, n, dim=axis))(v, rep, axis=1)
    scale = D ** -0.5
    scores = torch.einsum("bhqd,bhkd->bhqk", q, k) * scale
    p = _softmax(scores, axis=-1)
    return torch.einsum("bhqk,bhkd->bhqd", p, v)
```

```cpp
#include <cuda_runtime.h>
#include <cuda_bf16.h>
#include <cuda.h>
#include <stdint.h>

constexpr int NSC = 7;
constexpr int NSW = 4;
constexpr int FB0 = 32;
constexpr int FB = 24;
constexpr int FLA = 4;
constexpr int SWA = 5;
constexpr int SWZ = 53;
constexpr int TOTPOS = 13;
constexpr int PINSM = 0x3020;
constexpr int PINSF = 0x2c18;
constexpr int PINSS = 0x3018;
constexpr int LATE0 = 2200;
constexpr int LATE1 = 500;
constexpr int LATE2 = 300;
constexpr int LATE3 = 1000;

namespace {

constexpr int BH = 256, SQ = 608, SK = 1024, HD = 128;
constexpr int QT = 5;
constexpr int NTILES = BH * QT;
constexpr int NBLK = SK / 128;
constexpr int NST = 3;
constexpr int SPLIT_GRID = 132;
constexpr int SPLIT0 = 9 * SPLIT_GRID;
constexpr int NSPLIT = NTILES - SPLIT0;

constexpr uint32_t TILE_BYTES = 128 * 128 * 2;
constexpr uint32_t STAT_BYTES = 128 * 8;
constexpr uint32_t OFF_Q = 0;
constexpr uint32_t OFF_K = TILE_BYTES;
constexpr uint32_t OFF_V = OFF_K + NST * TILE_BYTES;
constexpr uint32_t OFF_STAT = OFF_V + NST * TILE_BYTES;
constexpr uint32_t BAR_FULL = OFF_STAT + STAT_BYTES;
constexpr uint32_t BAR_EMPTY = BAR_FULL + 8 * NST;
constexpr uint32_t BAR_Q0 = BAR_EMPTY + 8 * NST;
constexpr uint32_t BAR_Q = BAR_Q0 + 16;
constexpr uint32_t BAR_O = BAR_Q + 8;
constexpr uint32_t OFF_DUMMY = BAR_O + 8;
static_assert(OFF_DUMMY % 16 == 0, "");
constexpr uint32_t SMEM_BYTES = OFF_DUMMY + 16;

constexpr float SCALE_LOG2 = 0.08838834764831845f * 1.4426950408889634f;
constexpr float LAZY_LIMIT = 16777216.0f;

__device__ __align__(128) uint8_t g_part[NSPLIT][TILE_BYTES + STAT_BYTES];
__device__ uint32_t g_flag[NSPLIT];

__device__ __forceinline__ uint32_t smem_u32(const void* p) { return (uint32_t)__cvta_generic_to_shared(p); }
__device__ __forceinline__ bool elect_one() {
    uint32_t r;
    asm volatile("{\n.reg .pred p;\nelect.sync _|p, 0xffffffff;\nselp.u32 %0, 1, 0, p;\n}\n" : "=r"(r));
    return r != 0;
}
__device__ __forceinline__ void mbar_init(uint32_t bar, uint32_t count) {
    asm volatile("mbarrier.init.shared::cta.b64 [%0], %1;" ::"r"(bar), "r"(count) : "memory");
}
__device__ __forceinline__ void mbar_arrive(uint32_t bar) {
    asm volatile("mbarrier.arrive.shared::cta.b64 _, [%0];" ::"r"(bar) : "memory");
}
__device__ __forceinline__ void mbar_arrive_expect_tx(uint32_t bar, uint32_t bytes) {
    asm volatile("mbarrier.arrive.expect_tx.shared::cta.b64 _, [%0], %1;" ::"r"(bar), "r"(bytes) : "memory");
}
__device__ __forceinline__ void mbar_expect_tx(uint32_t bar, uint32_t bytes) {
    asm volatile("mbarrier.expect_tx.relaxed.cta.shared::cta.b64 [%0], %1;" ::"r"(bar), "r"(bytes) : "memory");
}
__device__ __forceinline__ void mbar_wait(uint32_t bar, uint32_t parity) {
    asm volatile(
        "{\n"
        ".reg .pred p;\n"
        ".reg .u32 cnt;\n"
        "mbarrier.try_wait.parity.shared::cta.b64 p, [%0], %1;\n"
        "@p bra DONE;\n"
        "mov.u32 cnt, 0;\n"
        "LOOP:\n"
        "mbarrier.try_wait.parity.shared::cta.b64 p, [%0], %1, 100000;\n"
        "@p bra DONE;\n"
        "add.u32 cnt, cnt, 1;\n"
        "setp.lt.u32 p, cnt, 20000;\n"
        "@p bra LOOP;\n"
        "trap;\n"
        "DONE:\n"
        "}\n" ::"r"(bar), "r"(parity) : "memory");
}
__device__ __forceinline__ uint32_t mbar_test(uint32_t bar, uint32_t parity) {
    uint32_t ok;
    asm volatile("{\n.reg .pred p;\nmbarrier.test_wait.parity.shared::cta.b64 p, [%1], %2;\nselp.u32 %0, 1, 0, p;\n}\n"
                 : "=r"(ok) : "r"(bar), "r"(parity) : "memory");
    return ok;
}
__device__ __forceinline__ void bar_sync(int id, int n) { asm volatile("bar.sync %0, %1;" ::"r"(id), "r"(n) : "memory"); }
__device__ __forceinline__ void bar_arrive(int id, int n) { asm volatile("bar.arrive %0, %1;" ::"r"(id), "r"(n) : "memory"); }
__device__ __forceinline__ void fence_async_smem() { asm volatile("fence.proxy.async.shared::cta;" ::: "memory"); }

__device__ __forceinline__ void tma_load_kv(uint32_t dst, const CUtensorMap* map, uint32_t bar, int row) {
    asm volatile("cp.async.bulk.tensor.3d.shared::cluster.global.mbarrier::complete_tx::bytes [%0], [%1, {%3, %4, %3}], [%2];"
                 ::"r"(dst), "l"(map), "r"(bar), "n"(0), "r"(row) : "memory");
}
__device__ __forceinline__ void tma_load_q(uint32_t dst, const CUtensorMap* map, uint32_t bar, int row, int head) {
    asm volatile("cp.async.bulk.tensor.4d.shared::cluster.global.mbarrier::complete_tx::bytes [%0], [%1, {%3, %4, %3, %5}], [%2];"
                 ::"r"(dst), "l"(map), "r"(bar), "n"(0), "r"(row), "r"(head) : "memory");
}
__device__ __forceinline__ void tma_store_o(const CUtensorMap* map, uint32_t src, int row, int half, int head) {
    asm volatile("cp.async.bulk.tensor.4d.global.shared::cta.bulk_group [%0, {%2, %3, %4, %5}], [%1];"
                 ::"l"(map), "r"(src), "n"(0), "r"(row), "r"(half), "r"(head) : "memory");
}
__device__ __forceinline__ void bulk_load(uint32_t dst, const void* src, uint32_t bytes, uint32_t bar) {
    asm volatile("cp.async.bulk.shared::cluster.global.mbarrier::complete_tx::bytes [%0], [%1], %2, [%3];"
                 ::"r"(dst), "l"(src), "r"(bytes), "r"(bar) : "memory");
}
__device__ __forceinline__ void bulk_store(void* dst, uint32_t src, uint32_t bytes) {
    asm volatile("cp.async.bulk.global.shared::cta.bulk_group [%0], [%1], %2;" ::"l"(dst), "r"(src), "r"(bytes) : "memory");
}
__device__ __forceinline__ void bulk_commit() { asm volatile("cp.async.bulk.commit_group;" ::: "memory"); }
__device__ __forceinline__ void bulk_wait_read() { asm volatile("cp.async.bulk.wait_group.read 0;" ::: "memory"); }
__device__ __forceinline__ void bulk_wait_all() { asm volatile("cp.async.bulk.wait_group 0;" ::: "memory"); }
__device__ __forceinline__ void l2_prefetch(const void* p, uint32_t bytes) {
    asm volatile("cp.async.bulk.prefetch.L2.global [%0], %1;" ::"l"(p), "r"(bytes) : "memory");
}

__device__ __forceinline__ void wg_fence() { asm volatile("wgmma.fence.sync.aligned;" ::: "memory"); }
__device__ __forceinline__ void wg_commit() { asm volatile("wgmma.commit_group.sync.aligned;" ::: "memory"); }
template <int N> __device__ __forceinline__ void wg_wait() { asm volatile("wgmma.wait_group.sync.aligned %0;" ::"n"(N) : "memory"); }

#define ACC8(a, o) "+f"(a[o + 0]), "+f"(a[o + 1]), "+f"(a[o + 2]), "+f"(a[o + 3]), "+f"(a[o + 4]), "+f"(a[o + 5]), "+f"(a[o + 6]), "+f"(a[o + 7])
#define ACC64(a) ACC8(a, 0), ACC8(a, 8), ACC8(a, 16), ACC8(a, 24), ACC8(a, 32), ACC8(a, 40), ACC8(a, 48), ACC8(a, 56)
#define REG64 "{%0,%1,%2,%3,%4,%5,%6,%7,%8,%9,%10,%11,%12,%13,%14,%15,%16,%17,%18,%19,%20,%21,%22,%23,%24,%25,%26,%27,%28,%29,%30,%31," \
              "%32,%33,%34,%35,%36,%37,%38,%39,%40,%41,%42,%43,%44,%45,%46,%47,%48,%49,%50,%51,%52,%53,%54,%55,%56,%57,%58,%59,%60,%61,%62,%63}"

template <int TRANS_B>
__device__ __forceinline__ void wgmma_rs(float (&d)[64], const uint32_t* a, uint32_t desc_lo, uint32_t desc_hi, uint32_t scale_d) {
    asm volatile(
        "{\n.reg .pred p;\n.reg .b64 db;\n"
        "setp.ne.b32 p, %70, 0;\n"
        "mov.b64 db, {%68, %69};\n"
        "wgmma.mma_async.sync.aligned.m64n128k16.f32.bf16.bf16 " REG64 ", {%64,%65,%66,%67}, db, p, 1, 1, %71;\n}\n"
        : ACC64(d)
        : "r"(a[0]), "r"(a[1]), "r"(a[2]), "r"(a[3]), "r"(desc_lo), "r"(desc_hi), "r"(scale_d), "n"(TRANS_B));
}
__device__ __forceinline__ void wgmma_ss(float (&d)[64], uint32_t adesc_lo, uint32_t bdesc_lo, uint32_t desc_hi, uint32_t scale_d) {
    asm volatile(
        "{\n.reg .pred p;\n.reg .b64 da, db;\n"
        "setp.ne.b32 p, %67, 0;\n"
        "mov.b64 da, {%64, %66};\n"
        "mov.b64 db, {%65, %66};\n"
        "wgmma.mma_async.sync.aligned.m64n128k16.f32.bf16.bf16 " REG64 ", da, db, p, 1, 1, 0, 0;\n}\n"
        : ACC64(d)
        : "r"(adesc_lo), "r"(bdesc_lo), "r"(desc_hi), "r"(scale_d));
}
__device__ __forceinline__ void fence_acc(float (&d)[64]) {
#pragma unroll
    for (int i = 0; i < 64; i++) asm volatile("" : "+f"(d[i])::"memory");
}
__device__ __forceinline__ void fence_u32(uint32_t (&d)[32]) {
#pragma unroll
    for (int i = 0; i < 32; i++) asm volatile("" : "+r"(d[i])::"memory");
}
__device__ __forceinline__ float ex2(float x) { float y; asm("ex2.approx.ftz.f32 %0, %1;" : "=f"(y) : "f"(x)); return y; }
__device__ __forceinline__ float rcp(float x) { float y; asm("rcp.approx.ftz.f32 %0, %1;" : "=f"(y) : "f"(x)); return y; }
__device__ __forceinline__ uint32_t pack_bf16(float lo, float hi) {
    uint32_t r; asm("cvt.rn.bf16x2.f32 %0, %1, %2;" : "=r"(r) : "f"(hi), "f"(lo)); return r;
}
__device__ __forceinline__ void mma_16816(float* d, const uint32_t* a, uint32_t b0, uint32_t b1) {
    asm volatile("mma.sync.aligned.m16n8k16.row.col.f32.bf16.bf16.f32 {%0,%1,%2,%3}, {%4,%5,%6,%7}, {%8,%9}, {%0,%1,%2,%3};"
                 : "+f"(d[0]), "+f"(d[1]), "+f"(d[2]), "+f"(d[3])
                 : "r"(a[0]), "r"(a[1]), "r"(a[2]), "r"(a[3]), "r"(b0), "r"(b1));
}
__device__ __forceinline__ void ldsm_x4(uint32_t* r, uint32_t addr) {
    asm volatile("ldmatrix.sync.aligned.m8n8.x4.shared.b16 {%0,%1,%2,%3}, [%4];"
                 : "=r"(r[0]), "=r"(r[1]), "=r"(r[2]), "=r"(r[3]) : "r"(addr) : "memory");
}
__device__ __forceinline__ void stsm_x4(uint32_t addr, uint32_t r0, uint32_t r1, uint32_t r2, uint32_t r3) {
    asm volatile("stmatrix.sync.aligned.m8n8.x4.shared.b16 [%0], {%1,%2,%3,%4};"
                 ::"r"(addr), "r"(r0), "r"(r1), "r"(r2), "r"(r3) : "memory");
}

template <int V> struct Int_ { static constexpr int value = V; };

constexpr uint32_t DESC_HI = (1024u >> 4) | (1u << 30);

template <int NREG>
__device__ __forceinline__ void issue_qk(float (&s)[64], const uint32_t (&q)[32], uint32_t qdesc, uint32_t kdesc) {
#pragma unroll
    for (int kk = 0; kk < 8; kk++) {
        const uint32_t kd = kdesc + (kk >> 2) * (16384 >> 4) + (kk & 3) * 2;
        if (kk < NREG) wgmma_rs<0>(s, &q[4 * kk], kd, DESC_HI, kk > 0);
        else wgmma_ss(s, qdesc + (kk >> 2) * (8192 >> 4) + (kk & 3) * 2, kd, DESC_HI, kk > 0);
    }
}
__device__ __forceinline__ void issue_pv(float (&o)[64], const uint32_t (&p)[32], uint32_t vdesc, uint32_t accumulate) {
#pragma unroll
    for (int kk = 0; kk < 8; kk++) {
        wgmma_rs<1>(o, &p[4 * kk], vdesc + kk * (2048 >> 4), DESC_HI, kk > 0 ? 1u : accumulate);
        if (kk == 3 || kk == 7) wg_commit();
    }
}

__device__ __forceinline__ void row_max(const float (&s)[64], float& m0, float& m1) {
    float a0 = fmaxf(s[0], s[1]), a1 = fmaxf(s[2], s[3]);
    float b0 = fmaxf(s[4], s[5]), b1 = fmaxf(s[6], s[7]);
#pragma unroll
    for (int j = 2; j < 16; j += 2) {
        a0 = fmaxf(a0, fmaxf(s[4 * j], s[4 * j + 1]));
        a1 = fmaxf(a1, fmaxf(s[4 * j + 2], s[4 * j + 3]));
        b0 = fmaxf(b0, fmaxf(s[4 * j + 4], s[4 * j + 5]));
        b1 = fmaxf(b1, fmaxf(s[4 * j + 6], s[4 * j + 7]));
    }
    m0 = fmaxf(a0, b0);
    m1 = fmaxf(a1, b1);
    m0 = fmaxf(m0, __shfl_xor_sync(0xffffffffu, m0, 1));
    m1 = fmaxf(m1, __shfl_xor_sync(0xffffffffu, m1, 1));
    m0 = fmaxf(m0, __shfl_xor_sync(0xffffffffu, m0, 2));
    m1 = fmaxf(m1, __shfl_xor_sync(0xffffffffu, m1, 2));
}

__device__ __forceinline__ void exp_pack(const float (&s)[64], uint32_t (&p)[32], float nm0, float nm1, float& r0, float& r1) {
    float a0, a1, b0, b1;
#pragma unroll
    for (int j = 0; j < 16; j++) {
        float e0 = ex2(fmaf(s[4 * j + 0], SCALE_LOG2, nm0));
        float e1 = ex2(fmaf(s[4 * j + 1], SCALE_LOG2, nm0));
        float e2 = ex2(fmaf(s[4 * j + 2], SCALE_LOG2, nm1));
        float e3 = ex2(fmaf(s[4 * j + 3], SCALE_LOG2, nm1));
        if (j == 0) { a0 = e0; b0 = e1; a1 = e2; b1 = e3; }
        else { a0 += e0; b0 += e1; a1 += e2; b1 += e3; }
        p[2 * j] = pack_bf16(e0, e1);
        p[2 * j + 1] = pack_bf16(e2, e3);
    }
    r0 = a0 + b0;
    r1 = a1 + b1;
}

__device__ __forceinline__ void pin(uint32_t dummy, float a, float b) {
    asm volatile("{\n.reg .pred p;\nsetp.gt.f32 p, %1, 0f7F000000;\n@p st.shared.f32 [%0], %2;\n}\n" ::"r"(dummy), "f"(a), "f"(b) : "memory");
}
template <uint32_t PINS, class Mid, class PvDone>
__device__ __forceinline__ void exp_pack_prog(float (&s)[64], uint32_t (&p)[32], float& nm0, float& nm1, float& r0, float& r1, uint32_t dummy,
                                              Mid mid, PvDone pv_done) {
#pragma unroll
    for (int i = 0; i < FB0; i++) s[i] = fmaf(s[i], SCALE_LOG2, (i & 2) ? nm1 : nm0);
#pragma unroll
    for (int j = 0; j < 64; j++) {
        s[j] = ex2(s[j]);
        if (j == 0) r0 = s[j];
        else if (j == 2) r1 = s[j];
        else if (j & 2) r1 += s[j];
        else r0 += s[j];
        if (j + 1 + FLA >= FB0 && (j + 1 + FLA - FB0) % FB == 0 && j + 1 + FLA < 64) {
            nm0 = __uint_as_float(__float_as_uint(nm0) | (__float_as_uint(r0) & 0x80000000u));
            nm1 = __uint_as_float(__float_as_uint(nm1) | (__float_as_uint(r1) & 0x80000000u));
#pragma unroll
            for (int i = j + 1 + FLA; i < j + 1 + FLA + FB; i++) if (i < 64) s[i] = fmaf(s[i], SCALE_LOG2, (i & 2) ? nm1 : nm0);
        }
        mid(j, (j & 2) ? r1 : r0);
        if ((j & 1) && j >= (int)((PINS >> (8 * (j >> 5))) & 255)) p[j >> 1] = pack_bf16(s[j - 1], s[j]);
#pragma unroll
        for (int g = 0; g < 2; g++) {
            if (j == (int)((PINS >> (8 * g)) & 255) - 1) {
                pin(dummy, r0, r1);
                if (g == 0) wg_wait<1>(); else wg_wait<0>();
                fence_u32(p);
#pragma unroll
                for (int i = 16 * g; i < 16 * g + 16; i++) if (2 * i + 1 <= j) p[i] = pack_bf16(s[2 * i], s[2 * i + 1]);
                if (g == 1) pv_done();
            }
        }
    }
}

template <bool SPLITTING>
struct Sched {
    int e_tile, e_n;
    int f_base, f_stride, nfull;
    int l_tile, l_n;
    int nseg;
    static __device__ __forceinline__ int first_tile(int c) {
        return SPLITTING ? c + (c < 40 ? 1200 : c < 80 ? 320 : c < 120 ? 1160 : 1068) : c;
    }
    __device__ __forceinline__ Sched() {
        const int c = blockIdx.x;
        if (SPLITTING) {
            const int k = (c >= 40) + (c >= 80) + (c >= 120);
            nfull = 9;
            f_stride = c < 120 ? 40 : 12;
            f_base = c + 320 * k;
            e_tile = first_tile(c);
            e_n = ((0x4206 >> (4 * k)) & 15) - (c < 28);
            l_tile = c + (c < 80 ? 1200 : 1108);
            l_n = c < 40 ? 0 : c < 80 ? 6 : c < 92 ? 4 : c < 120 ? 3 : 2;
            nseg = c < 80 ? 10 : 11;
        } else {
            e_tile = e_n = l_tile = l_n = 0;
            f_base = c; f_stride = gridDim.x;
            nseg = nfull = (NTILES - c + f_stride - 1) / f_stride;
        }
    }
    __device__ __forceinline__ int tile(int u) const {
        const int r = u - (e_n > 0);
        return r < 0 ? e_tile : (r < nfull ? f_base + r * f_stride : l_tile);
    }
    __device__ __forceinline__ int nblk(int u) const {
        const int r = u - (e_n > 0);
        return r < 0 ? e_n : (r < nfull ? NBLK : l_n);
    }
    __device__ __forceinline__ int kvrow(int u) const {
        const int r = u - (e_n > 0);
        return (tile(u) / QT) * SK + (r < nfull ? 0 : (NBLK - l_n) * 128);
    }
};

template <bool SPLITTING>
__global__ void __launch_bounds__(384, 1)
attn_kernel(const __grid_constant__ CUtensorMap tmQ, const __grid_constant__ CUtensorMap tmK,
            const __grid_constant__ CUtensorMap tmV, const __grid_constant__ CUtensorMap tmO,
            const __nv_bfloat16* __restrict__ gQ, const __nv_bfloat16* __restrict__ gK, __nv_bfloat16* __restrict__ gO) {
    extern __shared__ __align__(1024) uint8_t smem_raw[];
    const uint32_t sm = smem_u32(smem_raw);
    const int tid = threadIdx.x;
    const int warp = __shfl_sync(0xffffffffu, tid >> 5, 0);

    if (warp == 0) {
        if (elect_one()) {
            asm volatile("prefetch.tensormap [%0];" ::"l"(&tmK) : "memory");
            asm volatile("prefetch.tensormap [%0];" ::"l"(&tmQ) : "memory");
            asm volatile("prefetch.tensormap [%0];" ::"l"(&tmV) : "memory");
#pragma unroll
            for (int s = 0; s < NST; s++) {
                mbar_init(sm + BAR_FULL + 8 * s, 1);
                mbar_init(sm + BAR_EMPTY + 8 * s, 256);
            }
            mbar_init(sm + BAR_Q0, 1);
            mbar_init(sm + BAR_Q0 + 8, 1);
            mbar_init(sm + BAR_Q, 1);
            mbar_init(sm + BAR_O, 256);
            fence_async_smem();
            if (SPLITTING) {
                const uint32_t c = blockIdx.x;
                const uint32_t delay = c < 28 ? LATE0 : c < 40 ? LATE1 : c < 80 ? LATE2 : c - 92u < 28u ? LATE3 : 0;
                const uint32_t t0 = clock();
                while ((uint32_t)clock() - t0 < delay) {}
            }
            const int tile = Sched<SPLITTING>::first_tile(blockIdx.x), head = tile / QT, row = (tile - head * QT) * 128;
            mbar_arrive_expect_tx(sm + BAR_FULL, TILE_BYTES);
            tma_load_kv(sm + OFF_K, &tmK, sm + BAR_FULL, head * SK);
            mbar_arrive_expect_tx(sm + BAR_Q0, 16384);
            tma_load_q(sm + OFF_V, &tmQ, sm + BAR_Q0, row, head);
            mbar_arrive_expect_tx(sm + BAR_Q0 + 8, 16384);
            tma_load_q(sm + OFF_V + 16384, &tmQ, sm + BAR_Q0 + 8, row + 64, head);
            mbar_arrive_expect_tx(sm + BAR_FULL + 8, 2 * TILE_BYTES);
            tma_load_kv(sm + OFF_K + TILE_BYTES, &tmK, sm + BAR_FULL + 8, head * SK + 128);
            tma_load_kv(sm + OFF_V + TILE_BYTES, &tmV, sm + BAR_FULL + 8, head * SK);
            if (sm & 1023) __trap();
        }
    } else if (warp == 1) {
        uint32_t c;
        asm volatile("mov.u32 %0, %%ctaid.x;" : "=r"(c));
        if ((!SPLITTING || (c >= 28 && c - 92u >= 28u)) && elect_one()) {
            const int tile = Sched<SPLITTING>::first_tile(c), head = tile / QT, qt = tile - head * QT;
            const size_t kv = ((size_t)head * SK + (qt & 3) * 32) * HD;
            const __nv_bfloat16* qp = gQ + ((size_t)head * SQ + qt * 128) * HD;
            l2_prefetch(gK + kv, 32 * HD * 2);
            l2_prefetch(qp, 64 * HD * 2);
        }
    }
    __syncthreads();
    const Sched<SPLITTING> sc;

    if (warp < 4) {
        asm volatile("setmaxnreg.dec.sync.aligned.u32 24;");
        if (warp == 1) {
            int slot = 2; uint32_t ph = 1;
            int vrow = sc.kvrow(0) + 128;
#pragma unroll 1
            for (int u = 0; u < sc.nseg; u++) {
                const int n = sc.nblk(u);
                int krow = sc.kvrow(u) + (u == 0 ? 256 : 0);
                if (u == sc.nseg - 1 && sc.l_n > 0) {
                    uint32_t* flag = &g_flag[sc.l_tile - SPLIT0];
                    uint32_t v, cnt = 0;
                    do {
                        asm volatile("ld.acquire.gpu.global.u32 %0, [%1];" : "=r"(v) : "l"(flag) : "memory");
                        if (++cnt > 2000000u) __trap();
                    } while (v == 0);
                    asm volatile("fence.proxy.async.global;" ::: "memory");
                    __syncwarp();
                    if (elect_one()) asm volatile("st.relaxed.gpu.global.u32 [%0], %1;" ::"l"(flag), "r"(0u) : "memory");
                }
#pragma unroll 1
                for (int j = (u == 0 ? 2 : 0); j < n; j++) {
                    const uint32_t full = sm + BAR_FULL + 8 * slot;
                    mbar_wait(sm + BAR_EMPTY + 8 * slot, ph);
                    if (elect_one()) {
                        if (j == 0) mbar_expect_tx(full, 2 * TILE_BYTES);
                        else mbar_arrive_expect_tx(full, 2 * TILE_BYTES);
                        tma_load_kv(sm + OFF_K + slot * TILE_BYTES, &tmK, full, krow);
                        tma_load_kv(sm + OFF_V + slot * TILE_BYTES, &tmV, full, vrow);
                    }
                    if (j == 1 && u > 0) {
                        mbar_wait(sm + BAR_Q, (u - 1) & 1);
                        if (elect_one()) mbar_arrive(sm + BAR_FULL + 8 * (slot == 0 ? NST - 1 : slot - 1));
                    }
                    vrow = krow;
                    krow += 128;
                    if (++slot == NST) { slot = 0; ph ^= 1; }
                }
            }
            const uint32_t full = sm + BAR_FULL + 8 * slot;
            mbar_wait(sm + BAR_EMPTY + 8 * slot, ph);
            if (elect_one()) {
                mbar_arrive_expect_tx(full, sc.l_n > 0 ? 2 * TILE_BYTES + STAT_BYTES : TILE_BYTES);
                tma_load_kv(sm + OFF_V + slot * TILE_BYTES, &tmV, full, vrow);
                if (sc.l_n > 0) {
                    bulk_load(sm + OFF_K + slot * TILE_BYTES, g_part[sc.l_tile - SPLIT0], TILE_BYTES, full);
                    bulk_load(sm + OFF_STAT, g_part[sc.l_tile - SPLIT0] + TILE_BYTES, STAT_BYTES, full);
                }
            }
        } else if (warp == 2) {
            if (elect_one()) asm volatile("prefetch.tensormap [%0];" ::"l"(&tmO) : "memory");
            if (sc.nblk(0) > 2) {
                mbar_wait(sm + BAR_Q0 + 8, 0);
                __nanosleep(1000);
            }
#pragma unroll 1
            for (int u = 1; u <= sc.nseg; u++) {
                if (u > 1) {
                    mbar_wait(sm + BAR_O, u & 1);
                    if (elect_one()) {
                        if (u == 2 && sc.e_n > 0) {
                            bulk_store(g_part[sc.e_tile - SPLIT0], sm + OFF_Q, TILE_BYTES);
                            bulk_store(g_part[sc.e_tile - SPLIT0] + TILE_BYTES, sm + OFF_STAT, STAT_BYTES);
                            bulk_commit();
                            bulk_wait_all();
                            asm volatile("fence.proxy.async.global;" ::: "memory");
                            asm volatile("st.release.gpu.global.u32 [%0], %1;" ::"l"(&g_flag[sc.e_tile - SPLIT0]), "r"(1u) : "memory");
                        } else {
                            const int tile = sc.tile(u - 2), head = tile / QT, row = (tile - head * QT) * 128;
                            tma_store_o(&tmO, sm + OFF_Q, row, 0, head);
                            tma_store_o(&tmO, sm + OFF_Q + 16384, row + 64, 0, head);
                            bulk_commit();
                            bulk_wait_read();
                        }
                    }
                    __syncwarp();
                }
                if (u < sc.nseg) {
                    const int tile = sc.tile(u), head = tile / QT, row = (tile - head * QT) * 128;
                    if (elect_one()) {
                        mbar_arrive_expect_tx(sm + BAR_Q, TILE_BYTES);
                        tma_load_q(sm + OFF_Q, &tmQ, sm + BAR_Q, row, head);
                        tma_load_q(sm + OFF_Q + 16384, &tmQ, sm + BAR_Q, row + 64, head);
                    }
                }
            }
        }
    } else {
        asm volatile("setmaxnreg.inc.sync.aligned.u32 240;");
        const int wg = (warp >> 2) - 1;
        const int lane = tid & 31;
        const int my_bar = 1 + wg, other_bar = 2 - wg;
        const uint32_t qo_addr = sm + OFF_Q + wg * 16384 + ((warp & 3) * 16 + (lane & 15)) * 128 + (((lane >> 4) ^ (lane & 7)) << 4);
        const uint32_t qdesc = (((sm + OFF_Q + wg * 16384) & 0x3FFFF) >> 4) | (1u << 16);
        const uint32_t kdesc0 = (((sm + OFF_K) & 0x3FFFF) >> 4) | (1u << 16);
        const uint32_t vdesc0 = (((sm + OFF_V) & 0x3FFFF) >> 4) | ((16384u >> 4) << 16);

        float o[64], s[64];
        uint32_t q[32], p[32];
        uint32_t ot[32];
        float nm0, nm1, l0, l1;
        float i0, i1;

        auto row_totals = [&](float a0, float a1, float& t0, float& t1) {
            t0 = a0 + __shfl_xor_sync(0xffffffffu, a0, 1);
            t1 = a1 + __shfl_xor_sync(0xffffffffu, a1, 1);
            t0 += __shfl_xor_sync(0xffffffffu, t0, 2);
            t1 += __shfl_xor_sync(0xffffffffu, t1, 2);
        };
        auto padded_rows = [&](int u) { return sc.tile(u) % QT == QT - 1 && warp >= 10; };
        auto softmax_exact = [&](auto kind_tag, auto nreg_tag, uint32_t kaddr) {
            constexpr bool first = decltype(kind_tag)::value == 0;
            const uint32_t ka = kaddr + ((lane & 7) + ((lane >> 4) << 3)) * 128 + ((((lane >> 3) & 1) ^ (lane & 7)) << 4);
#pragma unroll
            for (int i = 0; i < 64; i++) s[i] = 0.f;
#pragma unroll
            for (int kk = 0; kk < 8; kk++) {
                uint32_t a[4];
                if (kk >= decltype(nreg_tag)::value) ldsm_x4(a, (qo_addr ^ ((kk & 3) << 5)) + (kk >> 2) * 8192);
                else { a[0] = q[4 * kk]; a[1] = q[4 * kk + 1]; a[2] = q[4 * kk + 2]; a[3] = q[4 * kk + 3]; }
#pragma unroll
                for (int nb = 0; nb < 8; nb++) {
                    uint32_t b[4];
                    ldsm_x4(b, (ka ^ ((kk & 3) << 5)) + (kk >> 2) * 16384 + nb * 2048);
                    mma_16816(&s[8 * nb], a, b[0], b[1]);
                    mma_16816(&s[8 * nb + 4], a, b[2], b[3]);
                }
            }
            float m0, m1;
            row_max(s, m0, m1);
            const float n0 = fminf(nm0, -m0 * SCALE_LOG2), n1 = fminf(nm1, -m1 * SCALE_LOG2);
            const float f0 = ex2(n0 - nm0), f1 = ex2(n1 - nm1);
            nm0 = n0; nm1 = n1;
            float r0, r1;
            exp_pack(s, p, nm0, nm1, r0, r1);
            l0 = l0 * f0 + r0;
            l1 = l1 * f1 + r1;
            if (!first) {
#pragma unroll
                for (int j = 0; j < 16; j++) { o[4 * j] *= f0; o[4 * j + 1] *= f0; o[4 * j + 2] *= f1; o[4 * j + 3] *= f1; }
            }
        };
        auto scale_o = [&](auto from_tag, auto to_tag) {
#pragma unroll
            for (int i = 8 * decltype(from_tag)::value; i < 8 * decltype(to_tag)::value; i++) {
                o[i] *= (i & 2) ? i1 : i0;
                asm volatile("" : "+f"(o[i])::"memory");
            }
        };
        auto pack_o = [&]() {
#pragma unroll
            for (int i = 0; i < 32; i++) {
                ot[i] = pack_bf16(o[2 * i], o[2 * i + 1]);
                asm volatile("" : "+r"(ot[i])::"memory");
            }
        };

        uint32_t toff = TILE_BYTES, boff = 8, ph = 0;

        int n = sc.nblk(0);
        float pad_next = padded_rows(1) ? -1e30f : 0.f;
        {
            float pad0 = padded_rows(0) ? -1e30f : 0.f;
            asm volatile("" : "+r"(n), "+f"(pad_next), "+f"(pad0) :: "memory");
            mbar_wait(sm + BAR_FULL, 0);
            mbar_wait(sm + BAR_Q0 + 8 * wg, 0);
            if (wg == 1) bar_sync(my_bar, 256);
            wg_fence();
            issue_qk<0>(s, q, qdesc + ((OFF_V - OFF_Q) >> 4), kdesc0);
            wg_commit();
            bar_arrive(other_bar, 256);
#pragma unroll
            for (int kk = 0; kk < 8; kk++) ldsm_x4(&q[4 * kk], (qo_addr ^ ((kk & 3) << 5)) + (kk >> 2) * 8192 + (OFF_V - OFF_Q));
            wg_wait<0>();
            fence_acc(s);
            mbar_arrive(sm + BAR_EMPTY);
            const float m0 = fmaxf(fmaxf(s[0], s[1]), fmaxf(s[4], s[5]));
            const float m1 = fmaxf(fmaxf(s[2], s[3]), fmaxf(s[6], s[7]));
            nm0 = fmaf(__shfl_sync(0xffffffffu, m0, 0, 4), -SCALE_LOG2, pad0);
            nm1 = fmaf(__shfl_sync(0xffffffffu, m1, 0, 4), -SCALE_LOG2, pad0);
            if (wg == 1) bar_sync(3, 256);
        }
#pragma unroll 1
        for (int redo = 0;; redo++) {
            exp_pack(s, p, nm0, nm1, l0, l1);
            if (redo || !__any_sync(0xffffffffu, !(l0 <= LAZY_LIMIT && l1 <= LAZY_LIMIT))) break;
            float m0, m1;
            row_max(s, m0, m1);
            nm0 = -m0 * SCALE_LOG2;
            nm1 = -m1 * SCALE_LOG2;
        }
        if (wg == 0) bar_arrive(3, 256);
        mbar_wait(sm + BAR_FULL + 8, 0);
        bar_sync(my_bar, 256);

        auto step = [&](auto kind_tag, int u, uint32_t accumulate, float pad_bias) {
            constexpr int KIND = decltype(kind_tag)::value;
            fence_acc(o); fence_u32(p); fence_acc(s);
            wg_fence();
            constexpr int QIN = KIND < 2 ? 0 : KIND == 3 ? NSW : 8;
            constexpr int QOUT = KIND == 0 ? 0 : KIND == 1 ? NSW : 8;
            issue_qk<QIN>(s, q, qdesc, kdesc0 + (toff >> 4));
            wg_commit();
            if (KIND == 1) {
                if (gQ != nullptr) {
                    scale_o(Int_<NSC>{}, Int_<8>{});
                    pack_o();
                    n = sc.nblk(u);
                    pad_next = padded_rows(u + 1) ? -1e30f : 0.f;
                } else {
#pragma unroll
                    for (int i = 0; i < 32; i++) { ot[i] = 0; asm volatile("" : "+r"(ot[i])::"memory"); }
                }
                fence_acc(o);
                wg_fence();
            }
            issue_pv(o, p, vdesc0 + (toff >> 4), accumulate);
            bar_arrive(other_bar, 256);
            const bool put_stats = KIND == 0 && u == 1 && (lane & 3) == 0;
            const uint32_t stat_addr = sm + OFF_STAT + ((warp - 4) * 16 + (lane >> 2)) * 8;
            if (put_stats) asm volatile("st.shared.v2.f32 [%0], {%1, %2};" ::"r"(stat_addr), "f"(nm0), "f"(nm1) : "memory");
            const uint32_t kaddr = sm + OFF_K + toff;
            const uint32_t rel = sm + BAR_EMPTY + boff;
            toff += TILE_BYTES; boff += 8;
            if (boff == 8 * NST) { toff = 0; boff = 0; ph ^= 1; }
            wg_wait<2>();
            fence_acc(s);
            float lo0, lo1;
            if (KIND == 0) {
                float m0 = fmaxf(fmaxf(s[0], s[1]), fmaxf(s[4], s[5]));
                float m1 = fmaxf(fmaxf(s[2], s[3]), fmaxf(s[6], s[7]));
                m0 = __shfl_sync(0xffffffffu, m0, 0, 4);
                m1 = __shfl_sync(0xffffffffu, m1, 0, 4);
                nm0 = fmaf(m0, -SCALE_LOG2, pad_bias);
                nm1 = fmaf(m1, -SCALE_LOG2, pad_bias);
                lo0 = l0; lo1 = l1;
                l0 = 0.f; l1 = 0.f;
            }
            float r0, r1;
            uint32_t ready;
            exp_pack_prog<KIND == 0 ? PINSF : KIND == 2 ? PINSM : PINSS>(
                s, p, nm0, nm1, r0, r1, sm + OFF_DUMMY,
                [&](int j, float r) {
                    const uint32_t z = __float_as_uint(r) & 0x80000000u;
                    if (KIND == 0 && j == TOTPOS) {
                        float t0, t1;
                        row_totals(__uint_as_float(__float_as_uint(lo0) | z), __uint_as_float(__float_as_uint(lo1) | z), t0, t1);
                        if (put_stats) asm volatile("st.shared.v2.f32 [%0], {%1, %2};" ::"r"(stat_addr + 64), "f"(t0), "f"(t1) : "memory");
                        i0 = rcp(t0); i1 = rcp(t1);
                    }
#pragma unroll
                    for (int kk = QIN; kk < QOUT; kk++) {
                        if (j == SWA + (kk - QIN) * (SWZ - SWA) / (QOUT - QIN > 1 ? QOUT - QIN - 1 : 1)) {
                            const uint32_t a = ((qo_addr ^ ((kk & 3) << 5)) | z) + (kk >> 2) * 8192;
                            ldsm_x4(&q[4 * kk], a);
                            stsm_x4(a, ot[4 * kk], ot[4 * kk + 1], ot[4 * kk + 2], ot[4 * kk + 3]);
                        }
                    }
                },
                [&]() {
                    ready = mbar_test(sm + BAR_FULL + boff, ph);
                    fence_acc(o);
                    if (KIND == 0) scale_o(Int_<0>{}, Int_<NSC>{});
                });
            if (KIND == 3) {
                fence_async_smem();
                mbar_arrive(sm + BAR_O);
            }
            uint32_t slow;
            asm volatile("{\n.reg .pred p;\nsetp.eq.u32 p, %3, 0;\nsetp.gtu.or.f32 p, %1, %4, p;\nsetp.gtu.or.f32 p, %2, %4, p;\n"
                         "vote.sync.any.pred p, p, 0xffffffff;\n"
                         "@!p mbarrier.arrive.shared::cta.b64 _, [%5];\n"
                         "selp.u32 %0, 1, 0, p;\n}\n"
                         : "=r"(slow) : "f"(r0), "f"(r1), "r"(ready), "f"(LAZY_LIMIT), "r"(rel) : "memory");
            bar_sync(my_bar, 256);
            if (__builtin_expect(slow, 0)) {
                if (__any_sync(0xffffffffu, !(r0 <= LAZY_LIMIT && r1 <= LAZY_LIMIT))) {
                    softmax_exact(kind_tag, Int_<QOUT>{}, kaddr);
                    r0 = 0.f; r1 = 0.f;
                }
                mbar_arrive(rel);
                mbar_wait(sm + BAR_FULL + boff, ph);
            }
            l0 += r0; l1 += r1;
            fence_u32(p);
        };

#pragma unroll 1
        for (int u = 0, j = 1;;) {
#pragma unroll 1
            for (; j < n; j++) step(Int_<2>{}, u, j > 1 ? 1u : 0u, 0.f);
            if (++u == sc.nseg) break;
            step(Int_<0>{}, u, 1u, pad_next);
            step(Int_<1>{}, u, 0u, 0.f);
            if (n == 2) {
#pragma unroll
                for (int i = 4 * NSW; i < 32; i++) q[i] = ot[i];
                break;
            }
            step(Int_<3>{}, u, 1u, 0.f);
            j = 3;
        }

        fence_acc(o); fence_u32(p);
        wg_fence();
        issue_pv(o, p, vdesc0 + (toff >> 4), 1u);
        if (wg == 0) bar_arrive(other_bar, 256);
        if (sc.l_n == 2) {
#pragma unroll
            for (int kk = NSW; kk < 8; kk++)
                stsm_x4((qo_addr ^ ((kk & 3) << 5)) + (kk >> 2) * 8192, q[4 * kk], q[4 * kk + 1], q[4 * kk + 2], q[4 * kk + 3]);
            fence_async_smem();
            mbar_arrive(sm + BAR_O);
        }
        auto finish = [&](auto merge_tag) {
            constexpr bool MERGE = decltype(merge_tag)::value;
            const uint32_t fin = qo_addr + (OFF_K - OFF_Q) + toff;
            const int tile = sc.tile(sc.nseg - 1), head = tile / QT, row = (tile - head * QT) * 128 + (warp - 4) * 16;
            const int c = lane & 7, r0 = lane >> 3;
            const uint32_t src = sm + OFF_K + toff + wg * 16384 + (warp & 3) * 2048 + r0 * 128;
            uint4* dst = reinterpret_cast<uint4*>(gO + ((size_t)head * SQ + row + r0) * HD) + c;
            float t0, t1;
            if (MERGE) {
#pragma unroll
                for (int kk = 0; kk < 8; kk++) ldsm_x4(&q[4 * kk], (fin ^ ((kk & 3) << 5)) + (kk >> 2) * 8192);
            }
            row_totals(l0, l1, t0, t1);
            if (MERGE) {
                const uint32_t a = sm + OFF_STAT + ((warp - 4) * 16 + (lane >> 2)) * 8;
                float pn0, pl0, pn1, pl1;
                asm volatile("ld.shared.v2.f32 {%0, %1}, [%2];" : "=f"(pn0), "=f"(pn1) : "r"(a) : "memory");
                asm volatile("ld.shared.v2.f32 {%0, %1}, [%2];" : "=f"(pl0), "=f"(pl1) : "r"(a + 64) : "memory");
                const float n0 = fminf(nm0, pn0), n1 = fminf(nm1, pn1);
                const float a0 = ex2(n0 - nm0), a1 = ex2(n1 - nm1);
                const float w0 = pl0 * ex2(n0 - pn0), w1 = pl1 * ex2(n1 - pn1);
                const float d0 = rcp(fmaf(t0, a0, w0)), d1 = rcp(fmaf(t1, a1, w1));
                i0 = a0 * d0; i1 = a1 * d1;
                const float c0 = w0 * d0, c1 = w1 * d1;
#pragma unroll
                for (int i = 0; i < 32; i++) {
                    s[2 * i] = __uint_as_float(q[i] << 16) * ((i & 1) ? c1 : c0);
                    s[2 * i + 1] = __uint_as_float(q[i] & 0xffff0000u) * ((i & 1) ? c1 : c0);
                }
                pin(sm + OFF_DUMMY, s[30], s[31]);
            } else {
                i0 = rcp(t0); i1 = rcp(t1);
                pin(sm + OFF_DUMMY, i0, i1);
            }
            wg_wait<0>();
            fence_acc(o);
#pragma unroll
            for (int h = 0; h < 2; h++) {
#pragma unroll
                for (int kk = 4 * h; kk < 4 * h + 4; kk++) {
                    uint32_t f[4];
#pragma unroll
                    for (int i = 0; i < 4; i++) {
                        const float ii = (i & 1) ? i1 : i0;
                        const int e = 8 * kk + 2 * i;
                        f[i] = MERGE ? pack_bf16(fmaf(o[e], ii, s[e]), fmaf(o[e + 1], ii, s[e + 1])) : pack_bf16(o[e] * ii, o[e + 1] * ii);
                    }
                    stsm_x4((fin ^ ((kk & 3) << 5)) + h * 8192, f[0], f[1], f[2], f[3]);
                }
                __syncwarp();
#pragma unroll
                for (int i = 0; i < 4; i++) {
                    uint4 v;
                    asm volatile("ld.shared.v4.u32 {%0,%1,%2,%3}, [%4];" : "=r"(v.x), "=r"(v.y), "=r"(v.z), "=r"(v.w)
                                 : "r"(src + h * 8192 + i * 512 + ((c ^ ((4 * i + r0) & 7)) << 4)) : "memory");
                    if (row < SQ) dst[i * 4 * (HD / 8) + h * 8] = v;
                }
            }
        };
        if (sc.l_n > 0) finish(Int_<1>{});
        else finish(Int_<0>{});
    }
}

typedef CUresult (*EncodeTiledFn)(CUtensorMap*, CUtensorMapDataType, cuuint32_t, void*, const cuuint64_t*, const cuuint64_t*,
                                  const cuuint32_t*, const cuuint32_t*, CUtensorMapInterleave, CUtensorMapSwizzle,
                                  CUtensorMapL2promotion, CUtensorMapFloatOOBfill);

}

extern "C" void kernel_launch(void* const* d_in, const int* in_sizes, int n_in, void* d_out, int out_size) {
    (void)in_sizes; (void)n_in; (void)out_size;
    static EncodeTiledFn encode = nullptr;
    static int num_sms = 0;
    if (!encode) {
        void* fn = nullptr;
        cudaDriverEntryPointQueryResult qr;
        cudaGetDriverEntryPoint("cuTensorMapEncodeTiled", &fn, cudaEnableDefault, &qr);
        encode = (EncodeTiledFn)fn;
        int dev = 0;
        cudaGetDevice(&dev);
        cudaDeviceGetAttribute(&num_sms, cudaDevAttrMultiProcessorCount, dev);
        cudaFuncSetAttribute(attn_kernel<true>, cudaFuncAttributeMaxDynamicSharedMemorySize, SMEM_BYTES);
        cudaFuncSetAttribute(attn_kernel<false>, cudaFuncAttributeMaxDynamicSharedMemorySize, SMEM_BYTES);
    }
    CUtensorMap tmQ, tmK, tmV, tmO;
    {
        cuuint64_t dims[4] = {64, SQ, 2, BH};
        cuuint64_t strides[3] = {HD * 2, 128, (cuuint64_t)SQ * HD * 2};
        cuuint32_t box[4] = {64, 64, 2, 1};
        cuuint32_t es[4] = {1, 1, 1, 1};
        encode(&tmQ, CU_TENSOR_MAP_DATA_TYPE_BFLOAT16, 4, d_in[0], dims, strides, box, es, CU_TENSOR_MAP_INTERLEAVE_NONE,
               CU_TENSOR_MAP_SWIZZLE_128B, CU_TENSOR_MAP_L2_PROMOTION_NONE, CU_TENSOR_MAP_FLOAT_OOB_FILL_NONE);
        encode(&tmO, CU_TENSOR_MAP_DATA_TYPE_BFLOAT16, 4, d_out, dims, strides, box, es, CU_TENSOR_MAP_INTERLEAVE_NONE,
               CU_TENSOR_MAP_SWIZZLE_128B, CU_TENSOR_MAP_L2_PROMOTION_NONE, CU_TENSOR_MAP_FLOAT_OOB_FILL_NONE);
    }
    {
        cuuint64_t dims[3] = {64, (cuuint64_t)BH * SK, 2};
        cuuint64_t strides[2] = {HD * 2, 128};
        cuuint32_t box[3] = {64, 128, 2};
        cuuint32_t es[3] = {1, 1, 1};
        encode(&tmK, CU_TENSOR_MAP_DATA_TYPE_BFLOAT16, 3, d_in[1], dims, strides, box, es, CU_TENSOR_MAP_INTERLEAVE_NONE,
               CU_TENSOR_MAP_SWIZZLE_128B, CU_TENSOR_MAP_L2_PROMOTION_NONE, CU_TENSOR_MAP_FLOAT_OOB_FILL_NONE);
        encode(&tmV, CU_TENSOR_MAP_DATA_TYPE_BFLOAT16, 3, d_in[2], dims, strides, box, es, CU_TENSOR_MAP_INTERLEAVE_NONE,
               CU_TENSOR_MAP_SWIZZLE_128B, CU_TENSOR_MAP_L2_PROMOTION_NONE, CU_TENSOR_MAP_FLOAT_OOB_FILL_NONE);
    }
    if (num_sms == SPLIT_GRID)
        attn_kernel<true><<<SPLIT_GRID, 384, SMEM_BYTES, cudaStreamPerThread>>>(tmQ, tmK, tmV, tmO, (const __nv_bfloat16*)d_in[0], (const __nv_bfloat16*)d_in[1], (__nv_bfloat16*)d_out);
    else
        attn_kernel<false><<<num_sms, 384, SMEM_BYTES, cudaStreamPerThread>>>(tmQ, tmK, tmV, tmO, (const __nv_bfloat16*)d_in[0], (const __nv_bfloat16*)d_in[1], (__nv_bfloat16*)d_out);
}
```
